```python
import torch

def _softmax(x, axis=-1):
    return torch.softmax(x, dim=axis)
def _gelu(x):
    return torch.nn.functional.gelu(x, approximate="tanh")
def _silu(x):
    return torch.nn.functional.silu(x)
def _sigmoid(x):
    return torch.sigmoid(x)
def _layernorm(x, axis=-1, eps=1e-5):
    m = x.mean(dim=axis, keepdim=True)
    v = x.var(dim=axis, keepdim=True, unbiased=False)
    return (x - m) / torch.sqrt(v + eps)
def _scatter_add(tgt, idx, src, axis=0):
    return tgt.clone().index_add_(axis, idx, src)
def _segment_sum(src, seg, n):
    out = torch.zeros((n,) + src.shape[1:], dtype=src.dtype)
    return out.index_add_(0, seg, src)
def _pad(x, pw):
    flat = tuple(v for pair in reversed(pw) for v in pair)
    return torch.nn.functional.pad(x, flat)

kernel_name = 'interleave_layers__sliding_local_dilated__mixer_s_mlp__prompt'

def setup_inputs():

    _w = (lambda a: (lambda t: t.to(torch.bfloat16) if t.is_floating_point() else t)(torch.as_tensor(a)))
    def _A_setup():
        B, S, D = 1, 2048, 512
        return {
            "x": _w((lambda *s: torch.randn(*s, dtype=torch.bfloat16) * 0.05)(B, S, D)),
            "wqkv": _w((lambda *s: torch.randn(*s, dtype=torch.bfloat16) * 0.1)(D, 3 * D)),
            "wo": _w((lambda *s: torch.randn(*s, dtype=torch.bfloat16) * 0.1)(D, D)),
        }
    _A_in = _A_setup()

    def _B_setup():
        B, S, D, F = 1, 2048, 512, 1792
        return {
            "x":  _w((lambda *s: torch.randn(*s, dtype=torch.bfloat16) * 0.05)(B, S, D)),
            "w1": _w((lambda *s: torch.randn(*s, dtype=torch.bfloat16) * 3.2)(D, D) * (D ** -0.5)),
            "w2": _w((lambda *s: torch.randn(*s, dtype=torch.bfloat16) * 3.2)(D, D) * (D ** -0.5)),
            "w3": _w((lambda *s: torch.randn(*s, dtype=torch.bfloat16) * 3.2)(D, F) * (D ** -0.5)),
            "w4": _w((lambda *s: torch.randn(*s, dtype=torch.bfloat16) * 3.2)(F, D) * (F ** -0.5)),
        }
    _B_in = _B_setup()

    return {
        "A_x": _A_in["x"],
        "A_wqkv": _A_in["wqkv"],
        "A_wo": _A_in["wo"],
        "B_x": _B_in["x"],
        "B_w1": _B_in["w1"],
        "B_w2": _B_in["w2"],
        "B_w3": _B_in["w3"],
        "B_w4": _B_in["w4"],
    }

def reference(A_x, A_wqkv, A_wo, B_x, B_w1, B_w2, B_w3, B_w4):
    def _A_ref(x, wqkv, wo):
        B, S, D = x.shape
        H = 32; Dh = D // H
        W, dil = 8, 2
        qkv = (lambda x, *d: x.permute(*d))((x @ wqkv).reshape(B, S, 3, H, Dh), 2, 0, 3, 1, 4)
        q, k, v = qkv[0], qkv[1], qkv[2]
        scale = Dh ** -0.5
        pos = torch.arange(S)
        off = torch.arange(W) * dil
        idx = pos[:, None] - off[None, :]
        mask = idx >= 0
        idx_c = torch.where(mask, idx, 0).reshape(-1)
        kg = k[:, :, idx_c, :].reshape(B, H, S, W, Dh)
        vg = v[:, :, idx_c, :].reshape(B, H, S, W, Dh)
        logits = torch.einsum("bhsd,bhswd->bhsw", q, kg) * scale
        logits = torch.where(mask[None, None, :, :], logits, -1e9)
        attn = _softmax(logits, axis=-1)
        o = torch.einsum("bhsw,bhswd->bhsd", attn, vg)
        return (lambda x, *d: x.permute(*d))(o, 0, 2, 1, 3).reshape(B, S, D) @ wo

    def _B_ref(x, w1, w2, w3, w4):
        B, S, D = x.shape
        h = _gelu(_layernorm(x, axis=-1) @ w1)
        c = D // 4
        g0 = _pad(h[:, :, 0*c:1*c], ((0, 0), (1, 0), (0, 0)))[:, :S, :]
        g1 = _pad(h[:, :, 1*c:2*c], ((0, 0), (0, 1), (0, 0)))[:, 1:, :]
        g2 = _pad(h[:, :, 2*c:3*c], ((0, 0), (2, 0), (0, 0)))[:, :S, :]
        g3 = _pad(h[:, :, 3*c:   ], ((0, 0), (0, 2), (0, 0)))[:, 2:, :]
        hs = torch.concatenate([g0, g1, g2, g3], axis=-1) @ w2
        x1 = x + hs
        h2 = _gelu(_layernorm(x1, axis=-1) @ w3) @ w4
        return x1 + h2

    x = A_x
    x = x + _A_ref(_layernorm(x, axis=-1), A_wqkv, A_wo)
    x = x + _B_ref(_layernorm(x, axis=-1), B_w1, B_w2, B_w3, B_w4)
    x = x + _A_ref(_layernorm(x, axis=-1), A_wqkv, A_wo)
    x = x + _B_ref(_layernorm(x, axis=-1), B_w1, B_w2, B_w3, B_w4)
    return x
```

```cpp
#include <cuda_runtime.h>
#include <cuda_bf16.h>
#include <cuda.h>
#include <stdint.h>

namespace fk {

template <int OFFA, int OFFB, uint32_t HIB>
__device__ __forceinline__ void wgmma_n64(float (&d)[32], uint32_t alo, uint32_t blo) {
  asm volatile("{\n.reg .pred p;\n.reg .b32 ta, tb;\n.reg .b64 da, db;\n"
    "add.u32 ta, %32, %34;\nmov.b64 da, {ta, 0x40000040};\n"
    "add.u32 tb, %33, %35;\nmov.b64 db, {tb, %36};\n"
    "setp.eq.u32 p, 0, 0;\n"
    "wgmma.mma_async.sync.aligned.m64n64k16.f32.bf16.bf16 "
    "{%0, %1, %2, %3, %4, %5, %6, %7, %8, %9, %10, %11, %12, %13, %14, %15, "
    "%16, %17, %18, %19, %20, %21, %22, %23, %24, %25, %26, %27, %28, %29, %30, %31}, "
    "da, db, p, 1, 1, 0, 1;\n}\n"
    : "+f"(d[0]), "+f"(d[1]), "+f"(d[2]), "+f"(d[3]), "+f"(d[4]), "+f"(d[5]), "+f"(d[6]), "+f"(d[7]),
      "+f"(d[8]), "+f"(d[9]), "+f"(d[10]), "+f"(d[11]), "+f"(d[12]), "+f"(d[13]), "+f"(d[14]), "+f"(d[15]),
      "+f"(d[16]), "+f"(d[17]), "+f"(d[18]), "+f"(d[19]), "+f"(d[20]), "+f"(d[21]), "+f"(d[22]), "+f"(d[23]),
      "+f"(d[24]), "+f"(d[25]), "+f"(d[26]), "+f"(d[27]), "+f"(d[28]), "+f"(d[29]), "+f"(d[30]), "+f"(d[31])
    : "r"(alo), "r"(blo), "n"(OFFA), "n"(OFFB), "n"(HIB));
}
template <int OFFA, int OFFB, uint32_t HIB>
__device__ __forceinline__ void wgmma_n96(float (&d)[48], uint32_t alo, uint32_t blo) {
  asm volatile("{\n.reg .pred p;\n.reg .b32 ta, tb;\n.reg .b64 da, db;\n"
    "add.u32 ta, %48, %50;\nmov.b64 da, {ta, 0x40000040};\n"
    "add.u32 tb, %49, %51;\nmov.b64 db, {tb, %52};\n"
    "setp.eq.u32 p, 0, 0;\n"
    "wgmma.mma_async.sync.aligned.m64n96k16.f32.bf16.bf16 "
    "{%0, %1, %2, %3, %4, %5, %6, %7, %8, %9, %10, %11, %12, %13, %14, %15, "
    "%16, %17, %18, %19, %20, %21, %22, %23, %24, %25, %26, %27, %28, %29, %30, %31, "
    "%32, %33, %34, %35, %36, %37, %38, %39, %40, %41, %42, %43, %44, %45, %46, %47}, "
    "da, db, p, 1, 1, 0, 1;\n}\n"
    : "+f"(d[0]), "+f"(d[1]), "+f"(d[2]), "+f"(d[3]), "+f"(d[4]), "+f"(d[5]), "+f"(d[6]), "+f"(d[7]),
      "+f"(d[8]), "+f"(d[9]), "+f"(d[10]), "+f"(d[11]), "+f"(d[12]), "+f"(d[13]), "+f"(d[14]), "+f"(d[15]),
      "+f"(d[16]), "+f"(d[17]), "+f"(d[18]), "+f"(d[19]), "+f"(d[20]), "+f"(d[21]), "+f"(d[22]), "+f"(d[23]),
      "+f"(d[24]), "+f"(d[25]), "+f"(d[26]), "+f"(d[27]), "+f"(d[28]), "+f"(d[29]), "+f"(d[30]), "+f"(d[31]),
      "+f"(d[32]), "+f"(d[33]), "+f"(d[34]), "+f"(d[35]), "+f"(d[36]), "+f"(d[37]), "+f"(d[38]), "+f"(d[39]),
      "+f"(d[40]), "+f"(d[41]), "+f"(d[42]), "+f"(d[43]), "+f"(d[44]), "+f"(d[45]), "+f"(d[46]), "+f"(d[47])
    : "r"(alo), "r"(blo), "n"(OFFA), "n"(OFFB), "n"(HIB));
}
template <int OFFA, int OFFB, uint32_t HIB>
__device__ __forceinline__ void wgmma_n128(float (&d)[64], uint32_t alo, uint32_t blo) {
  asm volatile("{\n.reg .pred p;\n.reg .b32 ta, tb;\n.reg .b64 da, db;\n"
    "add.u32 ta, %64, %66;\nmov.b64 da, {ta, 0x40000040};\n"
    "add.u32 tb, %65, %67;\nmov.b64 db, {tb, %68};\n"
    "setp.eq.u32 p, 0, 0;\n"
    "wgmma.mma_async.sync.aligned.m64n128k16.f32.bf16.bf16 "
    "{%0, %1, %2, %3, %4, %5, %6, %7, %8, %9, %10, %11, %12, %13, %14, %15, "
    "%16, %17, %18, %19, %20, %21, %22, %23, %24, %25, %26, %27, %28, %29, %30, %31, "
    "%32, %33, %34, %35, %36, %37, %38, %39, %40, %41, %42, %43, %44, %45, %46, %47, "
    "%48, %49, %50, %51, %52, %53, %54, %55, %56, %57, %58, %59, %60, %61, %62, %63}, "
    "da, db, p, 1, 1, 0, 1;\n}\n"
    : "+f"(d[0]), "+f"(d[1]), "+f"(d[2]), "+f"(d[3]), "+f"(d[4]), "+f"(d[5]), "+f"(d[6]), "+f"(d[7]),
      "+f"(d[8]), "+f"(d[9]), "+f"(d[10]), "+f"(d[11]), "+f"(d[12]), "+f"(d[13]), "+f"(d[14]), "+f"(d[15]),
      "+f"(d[16]), "+f"(d[17]), "+f"(d[18]), "+f"(d[19]), "+f"(d[20]), "+f"(d[21]), "+f"(d[22]), "+f"(d[23]),
      "+f"(d[24]), "+f"(d[25]), "+f"(d[26]), "+f"(d[27]), "+f"(d[28]), "+f"(d[29]), "+f"(d[30]), "+f"(d[31]),
      "+f"(d[32]), "+f"(d[33]), "+f"(d[34]), "+f"(d[35]), "+f"(d[36]), "+f"(d[37]), "+f"(d[38]), "+f"(d[39]),
      "+f"(d[40]), "+f"(d[41]), "+f"(d[42]), "+f"(d[43]), "+f"(d[44]), "+f"(d[45]), "+f"(d[46]), "+f"(d[47]),
      "+f"(d[48]), "+f"(d[49]), "+f"(d[50]), "+f"(d[51]), "+f"(d[52]), "+f"(d[53]), "+f"(d[54]), "+f"(d[55]),
      "+f"(d[56]), "+f"(d[57]), "+f"(d[58]), "+f"(d[59]), "+f"(d[60]), "+f"(d[61]), "+f"(d[62]), "+f"(d[63])
    : "r"(alo), "r"(blo), "n"(OFFA), "n"(OFFB), "n"(HIB));
}

constexpr int S_ = 2048, D_ = 512;
constexpr int NCTA = 128;
constexpr int NTHREADS = 512;

constexpr uint32_t SM_A = 0;
constexpr uint32_t SM_W = 131072;
constexpr int NWS = 5;
constexpr uint32_t SM_HALO_IN = 212992;
constexpr uint32_t SM_HALO_OUT = 217088;
constexpr uint32_t SM_XWG = 221184;
constexpr uint32_t SM_STATS = 225280;
constexpr uint32_t SM_CSUM = 226304;
constexpr uint32_t SM_CSTG = 228224;
constexpr uint32_t SM_BAR = 228480;
constexpr uint32_t SM_TOTAL = 229056;

constexpr uint32_t B_FULLW = 0;
constexpr uint32_t B_EMPTYW = 40;
constexpr uint32_t B_FULLA = 80;
constexpr uint32_t B_EMPTYA = 208;
constexpr uint32_t B_SFREE = 272;
constexpr uint32_t B_STG = 336;
constexpr uint32_t B_STAT = 400;
constexpr uint32_t B_HALOIN = 416, B_HALOOUT = 424, B_XWG = 432;
constexpr uint32_t B_CRDY = 440;
constexpr uint32_t B_PUBD = 512;

constexpr int BUF_O = 0, BUF_XA = 1, BUF_H = 2  , BUF_Y = 4, BUF_XB = 5, NBUF = 6;
constexpr int T_Q = 0, T_O = 1  , T_H2A0 = 5, T_H2A1 = 6,   T_H2B = 8, NTYPE = 9;

__device__ __align__(1024) __nv_bfloat16 g_act[NBUF * S_ * D_];
__device__ __align__(1024) __nv_bfloat16 g_h2a[S_ * 768];
__device__ __align__(1024) __nv_bfloat16 g_h2b[S_ * 1024];
__device__ __align__(1024) uint4 g_halo[2 * 128 * 256];
__device__ __align__(1024) float2 g_stats[2 * 3 * 32 * 8 * 64];
__device__ __align__(1024) float g_csum[8 * 4 * 480];
__device__ __align__(1024) uint32_t g_flags[2 * NTYPE * 32 * 32];
__device__ __align__(1024) uint32_t g_hflag[2 * 128 * 8];
__device__ __align__(1024) uint32_t g_cflag[8 * 64];
__device__ __align__(1024) uint32_t g_epoch[NCTA * 8];


struct KParams {
  CUtensorMap mXin, mActL, mActS, mOut, mH2aL, mH2aS, mH2a32, mH2bL, mH2bS, mWqkv, mWo, mW1, mW2, mW3, mW4;
  const __nv_bfloat16 *x, *wqkv, *wo, *w1, *w2, *w3, *w4;
};

__device__ __forceinline__ uint32_t smem_u32(const void* p) { return (uint32_t)__cvta_generic_to_shared(p); }
__device__ __forceinline__ void mbar_init(uint32_t bar, uint32_t cnt) {
  asm volatile("mbarrier.init.shared::cta.b64 [%0], %1;" ::"r"(bar), "r"(cnt) : "memory");
}
__device__ __forceinline__ void mbar_arrive(uint32_t bar) {
  asm volatile("mbarrier.arrive.shared::cta.b64 _, [%0];" ::"r"(bar) : "memory");
}
__device__ __forceinline__ void mbar_expect_tx(uint32_t bar, uint32_t bytes) {
  asm volatile("mbarrier.arrive.expect_tx.shared::cta.b64 _, [%0], %1;" ::"r"(bar), "r"(bytes) : "memory");
}
__device__ __forceinline__ bool mbar_try(uint32_t bar, uint32_t parity) {
  uint32_t ok;
  asm volatile("{\n.reg .pred p;\nmbarrier.try_wait.parity.shared::cta.b64 p, [%1], %2;\nselp.u32 %0, 1, 0, p;\n}"
               : "=r"(ok) : "r"(bar), "r"(parity) : "memory");
  return ok != 0;
}
constexpr uint32_t SPIN_BUDGET = 1u << 24;
struct Spin {
  uint32_t left;
  __device__ __forceinline__ bool fail(uint32_t cost = 1) {
    if (left < cost) return true;
    left -= cost;
    return false;
  }
};
__device__ __forceinline__ void mbar_wait(Spin& sp, uint32_t bar, uint32_t parity) {
  while (!mbar_try(bar, parity))
    if (sp.fail()) break;
}
__device__ __forceinline__ uint32_t ld_relaxed(const uint32_t* p) {
  uint32_t v;
  asm volatile("ld.relaxed.gpu.global.u32 %0, [%1];" : "=r"(v) : "l"(p) : "memory");
  return v;
}
__device__ __forceinline__ float2 ld_relaxed_f2(const float2* p) {
  float2 v;
  asm volatile("ld.relaxed.gpu.global.v2.f32 {%0, %1}, [%2];" : "=f"(v.x), "=f"(v.y) : "l"(p) : "memory");
  return v;
}
__device__ __forceinline__ void st_relaxed(uint32_t* p, uint32_t v) {
  asm volatile("st.relaxed.gpu.global.u32 [%0], %1;" ::"l"(p), "r"(v) : "memory");
}
__device__ __forceinline__ void tma_load_2d(uint32_t dst, const CUtensorMap* m, int c0, int c1, uint32_t bar) {
  asm volatile("cp.async.bulk.tensor.2d.shared::cluster.global.mbarrier::complete_tx::bytes [%0], [%1, {%3, %4}], [%2];"
               ::"r"(dst), "l"(m), "r"(bar), "r"(c0), "r"(c1) : "memory");
}
__device__ __forceinline__ void tma_load_2d_mc(uint32_t dst, const CUtensorMap* m, int c0, int c1, uint32_t bar) {
  asm volatile("cp.async.bulk.tensor.2d.shared::cluster.global.mbarrier::complete_tx::bytes.multicast::cluster"
               " [%0], [%1, {%3, %4}], [%2], %5;"
               ::"r"(dst), "l"(m), "r"(bar), "r"(c0), "r"(c1), "h"((uint16_t)3) : "memory");
}
__device__ __forceinline__ uint32_t mapa_peer(uint32_t addr, uint32_t rank) {
  uint32_t r;
  asm volatile("mapa.shared::cluster.u32 %0, %1, %2;" : "=r"(r) : "r"(addr), "r"(rank));
  return r;
}
__device__ __forceinline__ void mbar_arrive_remote(uint32_t bar_cluster) {
  asm volatile("mbarrier.arrive.relaxed.cluster.shared::cluster.b64 _, [%0];" ::"r"(bar_cluster) : "memory");
}
__device__ __forceinline__ void cluster_sync_relaxed() {
  asm volatile("barrier.cluster.arrive.relaxed.aligned;\nbarrier.cluster.wait.aligned;" ::: "memory");
}
__device__ __forceinline__ void tma_load_3d(uint32_t dst, const CUtensorMap* m, int c0, int c1, int c2, uint32_t bar) {
  asm volatile("cp.async.bulk.tensor.3d.shared::cluster.global.mbarrier::complete_tx::bytes [%0], [%1, {%3, %4, %5}], [%2];"
               ::"r"(dst), "l"(m), "r"(bar), "r"(c0), "r"(c1), "r"(c2) : "memory");
}
__device__ __forceinline__ void tma_load_4d(uint32_t dst, const CUtensorMap* m, int c0, int c1, int c2, int c3, uint32_t bar) {
  asm volatile("cp.async.bulk.tensor.4d.shared::cluster.global.mbarrier::complete_tx::bytes [%0], [%1, {%3, %4, %5, %6}], [%2];"
               ::"r"(dst), "l"(m), "r"(bar), "r"(c0), "r"(c1), "r"(c2), "r"(c3) : "memory");
}
__device__ __forceinline__ void tma_store_4d(const CUtensorMap* m, int c0, int c1, int c2, int c3, uint32_t src) {
  asm volatile("cp.async.bulk.tensor.4d.global.shared::cta.bulk_group [%0, {%2, %3, %4, %5}], [%1];"
               ::"l"(m), "r"(src), "r"(c0), "r"(c1), "r"(c2), "r"(c3) : "memory");
}
__device__ __forceinline__ void tma_store_2d(const CUtensorMap* m, int c0, int c1, uint32_t src) {
  asm volatile("cp.async.bulk.tensor.2d.global.shared::cta.bulk_group [%0, {%2, %3}], [%1];"
               ::"l"(m), "r"(src), "r"(c0), "r"(c1) : "memory");
}
__device__ __forceinline__ void tma_store_3d(const CUtensorMap* m, int c0, int c1, int c2, uint32_t src) {
  asm volatile("cp.async.bulk.tensor.3d.global.shared::cta.bulk_group [%0, {%2, %3, %4}], [%1];"
               ::"l"(m), "r"(src), "r"(c0), "r"(c1), "r"(c2) : "memory");
}
__device__ __forceinline__ void bulk_load(uint32_t dst, const void* src, uint32_t bytes, uint32_t bar) {
  asm volatile("cp.async.bulk.shared::cluster.global.mbarrier::complete_tx::bytes [%0], [%1], %2, [%3];"
               ::"r"(dst), "l"(src), "r"(bytes), "r"(bar) : "memory");
}
__device__ __forceinline__ void bulk_store(void* dst, uint32_t src, uint32_t bytes) {
  asm volatile("cp.async.bulk.global.shared::cta.bulk_group [%0], [%1], %2;" ::"l"(dst), "r"(src), "r"(bytes) : "memory");
}
__device__ __forceinline__ void bulk_commit() { asm volatile("cp.async.bulk.commit_group;" ::: "memory"); }
__device__ __forceinline__ void bulk_wait0() { asm volatile("cp.async.bulk.wait_group 0;" ::: "memory"); }
__device__ __forceinline__ void l2_prefetch(const void* p, uint32_t bytes) {
  asm volatile("cp.async.bulk.prefetch.L2.global [%0], %1;" ::"l"(p), "r"(bytes) : "memory");
}
__device__ __forceinline__ bool elect_one() {
  uint32_t ok;
  asm volatile("{\n.reg .pred p;\nelect.sync _|p, 0xffffffff;\nselp.u32 %0, 1, 0, p;\n}" : "=r"(ok));
  return ok != 0;
}
__device__ __forceinline__ void fence_release_gpu() {
  asm volatile("fence.proxy.async;" ::: "memory");
}
__device__ __forceinline__ void fence_acquire_for_tma() {
  asm volatile("fence.proxy.async.global;" ::: "memory");
}
__device__ __forceinline__ void fence_async_smem() { asm volatile("fence.proxy.async.shared::cta;" ::: "memory"); }
__device__ __forceinline__ void named_bar(int id, int n) { asm volatile("bar.sync %0, %1;" ::"r"(id), "r"(n) : "memory"); }

__device__ __forceinline__ void wg_fence() { asm volatile("wgmma.fence.sync.aligned;" ::: "memory"); }
__device__ __forceinline__ void wg_commit() { asm volatile("wgmma.commit_group.sync.aligned;" ::: "memory"); }
template <int N> __device__ __forceinline__ void wg_wait() { asm volatile("wgmma.wait_group.sync.aligned %0;" ::"n"(N) : "memory"); }
template <int N> __device__ __forceinline__ void zero_regs(float (&d)[N]) {
#pragma unroll
  for (int i = 0; i < N; i++) d[i] = 0.f;
}
template <int N> __device__ __forceinline__ void fence_regs(float (&d)[N]) {
#pragma unroll
  for (int i = 0; i < N; i++) asm volatile("" : "+f"(d[i])::"memory");
}
__device__ __forceinline__ uint32_t desc_lo(uint32_t addr, uint32_t lbo) { return ((addr & 0x3FFFF) >> 4) | ((lbo >> 4) << 16); }
constexpr uint32_t HI128 = 0x40000040u;
constexpr uint32_t HI64 = 0x80000020u;

__device__ __forceinline__ uint32_t pack2(float lo, float hi) {
  uint32_t r;
  asm("cvt.rn.bf16x2.f32 %0, %1, %2;" : "=r"(r) : "f"(hi), "f"(lo));
  return r;
}
__device__ __forceinline__ uint32_t badd2(uint32_t a, uint32_t b) {
  uint32_t r;
  asm("add.rn.bf16x2 %0, %1, %2;" : "=r"(r) : "r"(a), "r"(b));
  return r;
}
__device__ __forceinline__ float bf_lo(uint32_t v) { return __uint_as_float(v << 16); }
__device__ __forceinline__ float bf_hi(uint32_t v) { return __uint_as_float(v & 0xFFFF0000u); }
__device__ __forceinline__ void stsm4(uint32_t addr, uint32_t r0, uint32_t r1, uint32_t r2, uint32_t r3) {
  asm volatile("stmatrix.sync.aligned.m8n8.x4.shared.b16 [%0], {%1, %2, %3, %4};"
               ::"r"(addr), "r"(r0), "r"(r1), "r"(r2), "r"(r3) : "memory");
}
__device__ __forceinline__ void ldsm4(uint32_t addr, uint32_t& r0, uint32_t& r1, uint32_t& r2, uint32_t& r3) {
  asm volatile("ldmatrix.sync.aligned.m8n8.x4.shared.b16 {%0, %1, %2, %3}, [%4];"
               : "=r"(r0), "=r"(r1), "=r"(r2), "=r"(r3) : "r"(addr) : "memory");
}
__device__ __forceinline__ uint32_t movm_t(uint32_t a) {
  uint32_t d;
  asm volatile("movmatrix.sync.aligned.m8n8.trans.b16 %0, %1;" : "=r"(d) : "r"(a));
  return d;
}
__device__ __forceinline__ void mma16816(float (&c)[4], uint32_t a0, uint32_t a1, uint32_t a2, uint32_t a3, uint32_t b0, uint32_t b1) {
  asm volatile("mma.sync.aligned.m16n8k16.row.col.f32.bf16.bf16.f32 {%0,%1,%2,%3}, {%4,%5,%6,%7}, {%8,%9}, {%0,%1,%2,%3};"
               : "+f"(c[0]), "+f"(c[1]), "+f"(c[2]), "+f"(c[3])
               : "r"(a0), "r"(a1), "r"(a2), "r"(a3), "r"(b0), "r"(b1));
}
__device__ __forceinline__ void sts128(uint32_t addr, uint32_t a, uint32_t b, uint32_t c, uint32_t d) {
  asm volatile("st.shared.v4.b32 [%0], {%1, %2, %3, %4};" ::"r"(addr), "r"(a), "r"(b), "r"(c), "r"(d) : "memory");
}
__device__ __forceinline__ void lds128(uint32_t addr, uint32_t& a, uint32_t& b, uint32_t& c, uint32_t& d) {
  asm volatile("ld.shared.v4.b32 {%0, %1, %2, %3}, [%4];" : "=r"(a), "=r"(b), "=r"(c), "=r"(d) : "r"(addr) : "memory");
}
__device__ __forceinline__ float2 lds_f2(uint32_t addr) {
  float2 v;
  asm volatile("ld.shared.v2.f32 {%0, %1}, [%2];" : "=f"(v.x), "=f"(v.y) : "r"(addr) : "memory");
  return v;
}
__device__ __forceinline__ float2 lds_const_f2(uint32_t addr) {
  float2 v;
  asm("ld.shared.v2.f32 {%0, %1}, [%2];" : "=f"(v.x), "=f"(v.y) : "r"(addr));
  return v;
}
__device__ __forceinline__ void pin(uint32_t& v) { asm volatile("" : "+r"(v)::"memory"); }
__device__ __forceinline__ float gelu_half(float hx) {
  float u = hx * fmaf(hx * hx, 8.f * 0.035677408136300125f, 2.f * 0.7978845608028654f);
  float t;
  asm("tanh.approx.f32 %0, %1;" : "=f"(t) : "f"(u));
  return fmaf(hx, t, hx);
}
__device__ __forceinline__ float ex2f(float x) {
  float y;
  asm("ex2.approx.ftz.f32 %0, %1;" : "=f"(y) : "f"(x));
  return y;
}
__device__ __forceinline__ float quad_sum(float v) {
  v += __shfl_xor_sync(0xffffffffu, v, 1);
  v += __shfl_xor_sync(0xffffffffu, v, 2);
  return v;
}
__device__ __forceinline__ float quad_max(float v) {
  v = fmaxf(v, __shfl_xor_sync(0xffffffffu, v, 1));
  v = fmaxf(v, __shfl_xor_sync(0xffffffffu, v, 2));
  return v;
}
__device__ __forceinline__ uint32_t* flag_ptr(int l, int type, int blk) { return g_flags + ((l * NTYPE + type) * 32 + blk) * 32; }

constexpr int POLL_NS = 400;
constexpr int HALO_NS = 300;
constexpr int WLIM = 3;
#define BODY4(FN, BSTEP, HIB, ACC, ALO, BLO)                       \
  do {                                                             \
    const uint32_t _a = (ALO), _b = (BLO);                         \
    FN<0, 0, HIB>(ACC, _a, _b);                                    \
    FN<2, BSTEP, HIB>(ACC, _a, _b);                                \
    FN<4, 2 * BSTEP, HIB>(ACC, _a, _b);                            \
    FN<6, 3 * BSTEP, HIB>(ACC, _a, _b);                            \
  } while (0)

struct Cons {
  Spin sp;
  uint32_t sb, bar;
  uint32_t peer_emptyw;
  int h, w, lane, j, g, blk;
  uint32_t ws, wph;
  uint32_t amask;
  uint32_t sc;
  uint32_t stph;
  uint32_t dA, dW128, dW64;
  uint32_t stsm_row;
  uint32_t stsm_x;
  uint32_t r8;

  __device__ __forceinline__ void wait_w() {
    mbar_wait(sp, bar + B_FULLW + ws * 8, wph);
  }
  __device__ __forceinline__ void adv_w() { if (++ws == NWS) { ws = 0; wph ^= 1; } }
  __device__ __forceinline__ void rel_w(uint32_t slot) {
    if (lane == 0) mbar_arrive(bar + B_EMPTYW + slot * 8);
    if (lane == 1) mbar_arrive_remote(peer_emptyw + slot * 8);
  }
  __device__ __forceinline__ void wait_a(uint32_t pair) {
    mbar_wait(sp, bar + B_FULLA + h * 32 + pair * 8, (amask >> pair) & 1);
    amask ^= 1u << pair;
  }
  __device__ __forceinline__ void rel_a(uint32_t pair) { if (lane == 0) mbar_arrive(bar + B_EMPTYA + h * 32 + pair * 8); }
  __device__ __forceinline__ void signal_stage() {
    fence_async_smem();
    __syncwarp();
    if (lane == 0) mbar_arrive(bar + B_STG + h * 32 + (sc & 3) * 8);
    sc++;
  }
  __device__ __forceinline__ uint32_t slot_addr(uint32_t slot) const { return sb + SM_A + h * 65536 + slot * 8192; }
  __device__ __forceinline__ void put16(uint32_t tile, int i, uint32_t r0, uint32_t r1, uint32_t r2, uint32_t r3) const {
    stsm4(tile + stsm_row + (((2 * i + stsm_x) ^ r8) << 4), r0, r1, r2, r3);
  }
  __device__ __forceinline__ void put_tile(uint32_t tile, const uint32_t (&pk)[16]) const {
#pragma unroll
    for (int i = 0; i < 4; i++) put16(tile, i, pk[4 * i], pk[4 * i + 1], pk[4 * i + 2], pk[4 * i + 3]);
  }
};

template <bool WAIT_A>
__device__ __forceinline__ void n64_slot(Cons& c, float (&acc)[32], int pair) {
  c.wait_w();
  if (WAIT_A) c.wait_a(pair);
  wg_fence();
  const uint32_t a = c.dA + pair * 1024, b = c.dW128 + c.ws * 1024;
  BODY4(wgmma_n64, 128, HI128, acc, a, b);
  BODY4(wgmma_n64, 128, HI128, acc, a + 512, b + 512);
  wg_commit();
}

struct StatsRegs { float2 a0, a1, b0, b1; };
__device__ __forceinline__ void stats_issue(Cons& c, int l, int type, StatsRegs& s) {
  mbar_wait(c.sp, c.bar + B_STAT + c.h * 8, c.stph);
  c.stph ^= 1;
  const int q = c.lane & 3, gr = c.lane >> 2;
  const float2* p = g_stats + (((l * 3 + type) * 32 + c.blk) * 8 + 2 * q) * 64 + c.w * 16 + gr;
  s.a0 = ld_relaxed_f2(p); s.a1 = ld_relaxed_f2(p + 64); s.b0 = ld_relaxed_f2(p + 8); s.b1 = ld_relaxed_f2(p + 72);
}
__device__ __forceinline__ void stats_finish(const StatsRegs& s, float& mean0, float& var0, float& mean1, float& var1) {
  mean0 = quad_sum(s.a0.x + s.a1.x) * (1.f / 512.f);
  mean1 = quad_sum(s.b0.x + s.b1.x) * (1.f / 512.f);
  var0 = fmaxf(fmaf(-mean0, mean0, quad_sum(s.a0.y + s.a1.y) * (1.f / 512.f)), 0.f);
  var1 = fmaxf(fmaf(-mean1, mean1, quad_sum(s.b0.y + s.b1.y) * (1.f / 512.f)), 0.f);
}

template <bool STATS>
__device__ __forceinline__ void gemm_n64(Cons& c, float (&acc)[32], int l, int type, StatsRegs& st) {
  zero_regs(acc);
  n64_slot<true>(c, acc, 0);
  if (STATS) stats_issue(c, l, type, st);
  uint32_t prev = c.ws;
  c.adv_w();
#pragma unroll 1
  for (int i = 1; i < 4; i++) {
    n64_slot<true>(c, acc, i);
    wg_wait<1>();
    c.rel_w(prev);
    prev = c.ws;
    c.adv_w();
  }
  wg_wait<0>();
  c.rel_w(prev);
  fence_regs(acc);
}

__device__ __forceinline__ void put_stats(const Cons& c, const uint32_t (&pk)[16]) {
  float su[4] = {0, 0, 0, 0}, q0[4] = {0, 0, 0, 0}, q1[4] = {0, 0, 0, 0};
  const uint32_t ONES = 0x3F803F80u;
#pragma unroll
  for (int i = 0; i < 4; i++) {
    const uint32_t a0 = pk[4 * i], a1 = pk[4 * i + 1], a2 = pk[4 * i + 2], a3 = pk[4 * i + 3];
    mma16816(su, a0, a1, a2, a3, ONES, ONES);
    mma16816(q0, a0, a1, a2, a3, a0, a2);
    mma16816(q1, a0, a1, a2, a3, a1, a3);
  }
  const int q = c.lane & 3, gr = c.lane >> 2;
  if (q == (gr >> 1)) {
    const float d0 = (gr & 1) ? q0[1] : q0[0], d1 = (gr & 1) ? q1[3] : q1[2];
    const uint32_t addr = c.sb + SM_STATS + c.h * 512 + (c.w * 16 + gr) * 8;
    asm volatile("st.shared.v2.f32 [%0], {%1, %2};" ::"r"(addr), "f"(su[0]), "f"(d0) : "memory");
    asm volatile("st.shared.v2.f32 [%0], {%1, %2};" ::"r"(addr + 64), "f"(su[2]), "f"(d1) : "memory");
  }
}

__device__ __forceinline__ void consumer(const KParams& p, uint32_t sb, int h, int g, int j) {
  Cons c;
  c.sb = sb; c.bar = sb + SM_BAR; c.h = h; c.g = g; c.j = j; c.blk = 2 * g + h;
  c.peer_emptyw = mapa_peer(sb + SM_BAR + B_EMPTYW, (g & 1) ^ 1);
  c.lane = threadIdx.x & 31;
  c.w = __shfl_sync(0xffffffffu, (threadIdx.x >> 5) & 3, 0);
  c.sp.left = SPIN_BUDGET;
  c.ws = 0; c.wph = 0; c.amask = 0; c.sc = 0; c.stph = 0;
  c.dA = desc_lo(sb + SM_A + h * 65536, 16);
  c.dW128 = desc_lo(sb + SM_W, 8192);
  c.dW64 = desc_lo(sb + SM_W, 4096);
  c.r8 = c.lane & 7;
  c.stsm_x = c.lane >> 4;
  c.stsm_row = (c.w * 16 + ((c.lane >> 3) & 1) * 8 + c.r8) * 128;
  const int lane = c.lane, w = c.w;
  const int q = lane & 3, gr = lane >> 2;
  const uint32_t own = c.slot_addr(j);
  uint32_t csum = sb + SM_CSUM + q * 8;
  const float EPS = 1e-5f;

  uint32_t xres[16];
#pragma unroll
  for (int i = 0; i < 16; i++) xres[i] = 0;

#pragma unroll 1
  for (int l = 0; l < 2; l++) {
    if (l == 0) {
      mbar_wait(c.sp, c.bar + B_FULLA + h * 32 + (j >> 1) * 8, 0);
#pragma unroll
      for (int i = 0; i < 4; i++)
        ldsm4(own + c.stsm_row + (((2 * i + c.stsm_x) ^ c.r8) << 4), xres[4 * i], xres[4 * i + 1], xres[4 * i + 2], xres[4 * i + 3]);
      put_stats(c, xres);
      c.signal_stage();
    }
    uint32_t xa[16];
    uint32_t yv[16];
    StatsRegs st;
    {
      uint32_t kf[16], vt[16], qf[16];
      float rs0, rs1;
      float accQ[32];
      {
        float acc[64];
        float nm0, nm1;
        zero_regs(acc);
        uint32_t prev = 0;
#define KV_PAIR(PR)                                                                                    \
          c.wait_a(PR);                                                                                \
          _Pragma("unroll") for (int hf = 0; hf < 2; hf++) {                                           \
            c.wait_w();                                                                                \
            wg_fence();                                                                                \
            BODY4(wgmma_n128, 128, HI128, acc, c.dA + (PR) * 1024 + hf * 512, c.dW128 + c.ws * 1024);  \
            wg_commit();                                                                               \
            wg_wait<1>();                                                                              \
            if (hf == 1 || (PR) > 0) c.rel_w(prev);                                                    \
            prev = c.ws;                                                                               \
            c.adv_w();                                                                                 \
          }
        KV_PAIR(0)
        stats_issue(c, l, 0, st);
#pragma unroll 1
        for (int pr = 1; pr < 4; pr++) {
          KV_PAIR(pr)
        }
        {
          float mean0, var0, mean1, var1;
          stats_finish(st, mean0, var0, mean1, var1);
          rs0 = rsqrtf(var0 + EPS); rs1 = rsqrtf(var1 + EPS);
          nm0 = -mean0; nm1 = -mean1;
        }
        if (l == 0) mbar_wait(c.sp, c.bar + B_CRDY, 0);
        pin(csum);
#pragma unroll
        for (int t = 0; t < 8; t++) {
          float2 cc = lds_const_f2(csum + 512 + t * 32);
          accQ[4 * t] = nm0 * cc.x; accQ[4 * t + 1] = nm0 * cc.y; accQ[4 * t + 2] = nm1 * cc.x; accQ[4 * t + 3] = nm1 * cc.y;
        }
        n64_slot<false>(c, accQ, 0);
        const uint32_t q0 = c.ws;
        c.adv_w();
        n64_slot<false>(c, accQ, 1);
        const uint32_t q1 = c.ws;
        c.adv_w();
        float2 cc[16];
#pragma unroll
        for (int t = 0; t < 16; t++) cc[t] = lds_f2(csum + t * 32);
        wg_wait<2>();
        c.rel_w(prev);
        fence_regs(acc);
#pragma unroll
        for (int t = 0; t < 16; t++) {
          uint32_t a = pack2(fmaf(nm0, cc[t].x, acc[4 * t]) * rs0, fmaf(nm0, cc[t].y, acc[4 * t + 1]) * rs0);
          uint32_t b = pack2(fmaf(nm1, cc[t].x, acc[4 * t + 2]) * rs1, fmaf(nm1, cc[t].y, acc[4 * t + 3]) * rs1);
          if (t < 8) { kf[2 * t] = a; kf[2 * t + 1] = b; }
          else { vt[2 * (t - 8)] = movm_t(a); vt[2 * (t - 8) + 1] = movm_t(b); }
        }
        if (w == 3) {
          uint32_t dst = sb + (h ? SM_HALO_OUT : SM_XWG) + lane * 16;
#pragma unroll
          for (int v = 0; v < 4; v++) {
            sts128(dst + v * 512, kf[4 * v], kf[4 * v + 1], kf[4 * v + 2], kf[4 * v + 3]);
            sts128(dst + 2048 + v * 512, vt[4 * v], vt[4 * v + 1], vt[4 * v + 2], vt[4 * v + 3]);
          }
          fence_async_smem();
          __syncwarp();
          if (lane == 0) mbar_arrive(c.bar + (h ? B_HALOOUT : B_XWG));
        }
        wg_wait<1>();
        c.rel_w(q0);
        n64_slot<false>(c, accQ, 2);
        const uint32_t q2 = c.ws;
        c.adv_w();
        wg_wait<1>();
        c.rel_w(q1);
        n64_slot<false>(c, accQ, 3);
        const uint32_t q3 = c.ws;
        c.adv_w();
        wg_wait<1>();
        c.rel_w(q2);
        wg_wait<0>();
        c.rel_w(q3);
        fence_regs(accQ);
#pragma unroll
        for (int t = 0; t < 8; t++) {
          qf[2 * t] = pack2(accQ[4 * t] * rs0, accQ[4 * t + 1] * rs0);
          qf[2 * t + 1] = pack2(accQ[4 * t + 2] * rs1, accQ[4 * t + 3] * rs1);
        }
      }
      const uint32_t bandK = c.slot_addr((j + 1) & 7), bandV = c.slot_addr((j + 2) & 7);
      if (w < 3) {
#pragma unroll
        for (int v = 0; v < 4; v++) {
          sts128(bandK + w * 2048 + v * 512 + lane * 16, kf[4 * v], kf[4 * v + 1], kf[4 * v + 2], kf[4 * v + 3]);
          sts128(bandV + w * 2048 + v * 512 + lane * 16, vt[4 * v], vt[4 * v + 1], vt[4 * v + 2], vt[4 * v + 3]);
        }
      }
      float s2[4][4], s3[4][4];
#pragma unroll
      for (int hd = 0; hd < 4; hd++) {
#pragma unroll
        for (int i = 0; i < 4; i++) { s2[hd][i] = 0.f; s3[hd][i] = 0.f; }
        mma16816(s2[hd], qf[4 * hd], qf[4 * hd + 1], qf[4 * hd + 2], qf[4 * hd + 3], kf[4 * hd], kf[4 * hd + 2]);
        mma16816(s3[hd], qf[4 * hd], qf[4 * hd + 1], qf[4 * hd + 2], qf[4 * hd + 3], kf[4 * hd + 1], kf[4 * hd + 3]);
      }
      named_bar(1 + h, 128);
      uint32_t srcK, srcV;
      const bool noprev = (c.blk == 0) && (w == 0);
      if (w > 0) { srcK = bandK + (w - 1) * 2048; srcV = bandV + (w - 1) * 2048; }
      else if (h == 1) { mbar_wait(c.sp, c.bar + B_XWG, l); srcK = sb + SM_XWG; srcV = srcK + 2048; }
      else { if (g > 0) mbar_wait(c.sp, c.bar + B_HALOIN, l); srcK = sb + SM_HALO_IN; srcV = srcK + 2048; }
      uint32_t pk[16], pv[16];
#pragma unroll
      for (int hd = 0; hd < 4; hd++) lds128(srcK + hd * 512 + lane * 16, pk[4 * hd], pk[4 * hd + 1], pk[4 * hd + 2], pk[4 * hd + 3]);
#pragma unroll
      for (int hd = 0; hd < 4; hd++) lds128(srcV + hd * 512 + lane * 16, pv[4 * hd], pv[4 * hd + 1], pv[4 * hd + 2], pv[4 * hd + 3]);
      if (noprev) {
#pragma unroll
        for (int i = 0; i < 16; i++) { pk[i] = 0; pv[i] = 0; }
      }
      const bool par = gr & 1;
      const bool lo = (2 * q + (gr & 1)) <= gr;
      const float SCL = 0.25f * 1.4426950408889634f;
      float m0[4], e0[4], m1[4], e1[4];
#pragma unroll
      for (int hd = 0; hd < 4; hd++) {
        float s0[4] = {0, 0, 0, 0}, s1[4] = {0, 0, 0, 0};
        mma16816(s0, qf[4 * hd], qf[4 * hd + 1], qf[4 * hd + 2], qf[4 * hd + 3], pk[4 * hd], pk[4 * hd + 2]);
        mma16816(s1, qf[4 * hd], qf[4 * hd + 1], qf[4 * hd + 2], qf[4 * hd + 3], pk[4 * hd + 1], pk[4 * hd + 3]);
        m0[hd] = par ? s1[1] : s1[0];
        e0[hd] = lo ? (par ? s2[hd][1] : s2[hd][0]) : (par ? s0[1] : s0[0]);
        m1[hd] = par ? s2[hd][3] : s2[hd][2];
        e1[hd] = lo ? (par ? s3[hd][3] : s3[hd][2]) : (par ? s1[3] : s1[2]);
      }
      if (noprev) {
#pragma unroll
        for (int hd = 0; hd < 4; hd++) { m0[hd] = -INFINITY; if (!lo) { e0[hd] = -INFINITY; e1[hd] = -INFINITY; } }
      }
      float mx0[4], mx1[4];
#pragma unroll
      for (int hd = 0; hd < 4; hd++) { mx0[hd] = fmaxf(m0[hd], e0[hd]); mx1[hd] = fmaxf(m1[hd], e1[hd]); }
#pragma unroll
      for (int sft = 1; sft <= 2; sft <<= 1)
#pragma unroll
        for (int hd = 0; hd < 4; hd++) {
          mx0[hd] = fmaxf(mx0[hd], __shfl_xor_sync(0xffffffffu, mx0[hd], sft));
          mx1[hd] = fmaxf(mx1[hd], __shfl_xor_sync(0xffffffffu, mx1[hd], sft));
        }
      float z0[4], z1[4];
#pragma unroll
      for (int hd = 0; hd < 4; hd++) {
        m0[hd] = ex2f((m0[hd] - mx0[hd]) * SCL); e0[hd] = ex2f((e0[hd] - mx0[hd]) * SCL);
        m1[hd] = ex2f((m1[hd] - mx1[hd]) * SCL); e1[hd] = ex2f((e1[hd] - mx1[hd]) * SCL);
        z0[hd] = m0[hd] + e0[hd]; z1[hd] = m1[hd] + e1[hd];
      }
#pragma unroll
      for (int sft = 1; sft <= 2; sft <<= 1)
#pragma unroll
        for (int hd = 0; hd < 4; hd++) {
          z0[hd] += __shfl_xor_sync(0xffffffffu, z0[hd], sft);
          z1[hd] += __shfl_xor_sync(0xffffffffu, z1[hd], sft);
        }
      uint32_t ov[16];
      const uint32_t psel = par ? 0x1044u : 0x4410u;
#pragma unroll
      for (int hd = 0; hd < 4; hd++) {
        const float i0 = __fdividef(1.f, z0[hd]), i1 = __fdividef(1.f, z1[hd]);
        const uint32_t t0 = pack2(m0[hd] * i0, e0[hd] * i0), t1 = pack2(m1[hd] * i1, e1[hd] * i1);
        const uint32_t pm0 = __byte_perm(t0, 0u, psel), pm1 = __byte_perm(t1, 0u, psel);
        const uint32_t pe0 = __byte_perm(t0 >> 16, 0u, psel), pe1 = __byte_perm(t1 >> 16, 0u, psel);
        float o0[4] = {0, 0, 0, 0}, o1[4] = {0, 0, 0, 0};
        const uint32_t x0 = lo ? 0u : pe0, x3 = lo ? 0u : pe1, y0 = lo ? pe0 : 0u, y3 = lo ? pe1 : 0u;
        mma16816(o0, x0, 0u, pm0, x3, pv[4 * hd], pv[4 * hd + 1]);
        mma16816(o1, x0, 0u, pm0, x3, pv[4 * hd + 2], pv[4 * hd + 3]);
        mma16816(o0, y0, pm1, 0u, y3, vt[4 * hd], vt[4 * hd + 1]);
        mma16816(o1, y0, pm1, 0u, y3, vt[4 * hd + 2], vt[4 * hd + 3]);
        ov[4 * hd] = pack2(o0[0], o0[1]); ov[4 * hd + 1] = pack2(o0[2], o0[3]);
        ov[4 * hd + 2] = pack2(o1[0], o1[1]); ov[4 * hd + 3] = pack2(o1[2], o1[3]);
      }
      named_bar(1 + h, 128);
      c.put_tile(own, ov);
      c.signal_stage();
    }
    {
      float acc[32];
      gemm_n64<false>(c, acc, l, 0, st);
#pragma unroll
      for (int t = 0; t < 8; t++) {
        xa[2 * t] = badd2(xres[2 * t], pack2(acc[4 * t], acc[4 * t + 1]));
        xa[2 * t + 1] = badd2(xres[2 * t + 1], pack2(acc[4 * t + 2], acc[4 * t + 3]));
      }
      c.put_tile(own, xa);
      put_stats(c, xa);
      c.signal_stage();
    }
    {
      float acc[32];
      gemm_n64<true>(c, acc, l, 1, st);
      float mean0, var0, mean1, var1;
      stats_finish(st, mean0, var0, mean1, var1);
      const float r0 = rsqrtf(var0 + EPS), r1 = rsqrtf(var1 + EPS);
      const float rs0 = 0.5f * r0 * rsqrtf(var0 * r0 * r0 + EPS), rs1 = 0.5f * r1 * rsqrtf(var1 * r1 * r1 + EPS);
      const float nm0 = -mean0 * rs0, nm1 = -mean1 * rs1;
      if (l == 0) mbar_wait(c.sp, c.bar + B_CRDY + 8, 0);
      pin(csum);
      uint32_t hv[16];
      float2 cc[8];
#pragma unroll
      for (int t = 0; t < 8; t++) cc[t] = lds_f2(csum + 768 + t * 32);
#pragma unroll
      for (int t = 0; t < 8; t++) {
        hv[2 * t] = pack2(gelu_half(fmaf(acc[4 * t], rs0, nm0 * cc[t].x)), gelu_half(fmaf(acc[4 * t + 1], rs0, nm0 * cc[t].y)));
        hv[2 * t + 1] = pack2(gelu_half(fmaf(acc[4 * t + 2], rs1, nm1 * cc[t].x)), gelu_half(fmaf(acc[4 * t + 3], rs1, nm1 * cc[t].y)));
      }
      c.put_tile(own, hv);
      c.signal_stage();
#pragma unroll
      for (int t = 0; t < 8; t++) {
        yv[2 * t] = pack2((bf_lo(xa[2 * t]) - mean0) * r0, (bf_hi(xa[2 * t]) - mean0) * r0);
        yv[2 * t + 1] = pack2((bf_lo(xa[2 * t + 1]) - mean1) * r1, (bf_hi(xa[2 * t + 1]) - mean1) * r1);
      }
    }
    {
      float acc[32];
      gemm_n64<false>(c, acc, l, 0, st);
#pragma unroll
      for (int t = 0; t < 8; t++) {
        yv[2 * t] = badd2(yv[2 * t], pack2(acc[4 * t], acc[4 * t + 1]));
        yv[2 * t + 1] = badd2(yv[2 * t + 1], pack2(acc[4 * t + 2], acc[4 * t + 3]));
      }
      c.put_tile(own, yv);
      put_stats(c, yv);
      c.signal_stage();
    }
    {
      float accA[48], accB[64];
      zero_regs(accA);
      float rs0, nm0, rs1, nm1;
      uint32_t prev = 0;
#define PASSA_PAIR(PR)                                                                                 \
        c.wait_a(PR);                                                                                  \
        _Pragma("unroll") for (int hf = 0; hf < 2; hf++) {                                             \
          c.wait_w();                                                                                  \
          wg_fence();                                                                                  \
          BODY4(wgmma_n96, 64, HI64, accA, c.dA + (PR) * 1024 + hf * 512, c.dW64 + c.ws * 1024);       \
          wg_commit();                                                                                 \
          wg_wait<1>();                                                                                \
          if (hf == 1 || (PR) > 0) c.rel_w(prev);                                                      \
          prev = c.ws;                                                                                 \
          c.adv_w();                                                                                   \
        }
      PASSA_PAIR(0)
      stats_issue(c, l, 2, st);
#pragma unroll 1
      for (int pr = 1; pr < 4; pr++) { PASSA_PAIR(pr) }
      {
        float mean0, var0, mean1, var1;
        stats_finish(st, mean0, var0, mean1, var1);
        rs0 = 0.5f * rsqrtf(var0 + EPS); rs1 = 0.5f * rsqrtf(var1 + EPS);
        nm0 = -mean0; nm1 = -mean1;
      }
      if (l == 0) mbar_wait(c.sp, c.bar + B_CRDY + 16, 0);
      pin(csum);
#pragma unroll
      for (int t = 0; t < 16; t++) {
        float2 cc = lds_const_f2(csum + 1024 + 384 + t * 32);
        accB[4 * t] = nm0 * cc.x; accB[4 * t + 1] = nm0 * cc.y; accB[4 * t + 2] = nm1 * cc.x; accB[4 * t + 3] = nm1 * cc.y;
      }
      const uint32_t s0a = c.slot_addr(0), s1a = c.slot_addr(1);
#define PASSB_ISSUE(KB)                                                                 \
      c.wait_w();                                                                       \
      wg_fence();                                                                       \
      BODY4(wgmma_n128, 64, HI64, accB, c.dA + (KB) * 512, c.dW64 + c.ws * 1024);       \
      wg_commit();
#define PASSB_NEXT() wg_wait<1>(); c.rel_w(prev); prev = c.ws; c.adv_w();
#define GELUA(T0, T1)                                                                   \
      _Pragma("unroll") for (int t = (T0); t < (T1); t++) {                             \
        ha[2 * t] = pack2(gelu_half(fmaf(nm0, ca[t].x, accA[4 * t]) * rs0), gelu_half(fmaf(nm0, ca[t].y, accA[4 * t + 1]) * rs0)); \
        ha[2 * t + 1] = pack2(gelu_half(fmaf(nm1, ca[t].x, accA[4 * t + 2]) * rs1), gelu_half(fmaf(nm1, ca[t].y, accA[4 * t + 3]) * rs1)); \
      }
      float2 ca[12];
      uint32_t ha[24];
      PASSB_ISSUE(0)
#pragma unroll
      for (int t = 0; t < 12; t++) ca[t] = lds_f2(csum + 1024 + t * 32);
      PASSB_NEXT()
      fence_regs(accA);
      PASSB_ISSUE(1)
      GELUA(0, 8)
#pragma unroll
      for (int t = 0; t < 16; t++) asm volatile("" : "+r"(ha[t]));
      PASSB_NEXT()
      PASSB_ISSUE(2)
#pragma unroll
      for (int i = 0; i < 4; i++) c.put16(s0a, i, ha[4 * i], ha[4 * i + 1], ha[4 * i + 2], ha[4 * i + 3]);
      c.signal_stage();
      GELUA(8, 12)
      PASSB_NEXT()
      PASSB_ISSUE(3)
      {
        const uint32_t row = ((lane >> 3) & 1) * 8 + c.r8;
#pragma unroll
        for (int i = 0; i < 2; i++)
          stsm4(s1a + w * 2048 + row * 64 + (((2 * i + c.stsm_x) ^ ((row >> 1) & 3)) << 4),
                ha[16 + 4 * i], ha[17 + 4 * i], ha[18 + 4 * i], ha[19 + 4 * i]);
      }
      c.signal_stage();
      PASSB_NEXT()
#pragma unroll 1
      for (int kb = 4; kb < 8; kb++) {
        PASSB_ISSUE(kb)
        PASSB_NEXT()
        if (kb == 4 || kb == 6) c.rel_a((kb - 2) >> 1);
      }
      wg_wait<0>();
      c.rel_w(prev);
      fence_regs(accB);
      const uint32_t s6a = c.slot_addr(6), s7a = c.slot_addr(7);
      float acc[32];
      zero_regs(acc);
      {
        uint32_t hv[16];
#pragma unroll
        for (int t = 0; t < 8; t++) {
          hv[2 * t] = pack2(gelu_half(accB[4 * t] * rs0), gelu_half(accB[4 * t + 1] * rs0));
          hv[2 * t + 1] = pack2(gelu_half(accB[4 * t + 2] * rs1), gelu_half(accB[4 * t + 3] * rs1));
        }
        c.put_tile(s6a, hv);
        c.signal_stage();
      }
      n64_slot<true>(c, acc, 1);
      const uint32_t w40 = c.ws; c.adv_w();
      n64_slot<true>(c, acc, 2);
      prev = c.ws; c.adv_w();
      {
        uint32_t hv[16];
#pragma unroll
        for (int t = 0; t < 4; t++) {
          hv[2 * t] = pack2(gelu_half(accB[32 + 4 * t] * rs0), gelu_half(accB[32 + 4 * t + 1] * rs0));
          hv[2 * t + 1] = pack2(gelu_half(accB[32 + 4 * t + 2] * rs1), gelu_half(accB[32 + 4 * t + 3] * rs1));
        }
        wg_wait<1>();
        c.rel_a(1);
        c.rel_w(w40);
#pragma unroll
        for (int t = 4; t < 8; t++) {
          hv[2 * t] = pack2(gelu_half(accB[32 + 4 * t] * rs0), gelu_half(accB[32 + 4 * t + 1] * rs0));
          hv[2 * t + 1] = pack2(gelu_half(accB[32 + 4 * t + 2] * rs1), gelu_half(accB[32 + 4 * t + 3] * rs1));
        }
        c.put_tile(s7a, hv);
        c.signal_stage();
      }
#pragma unroll 1
      for (int i = 2; i < 14; i++) {
        const uint32_t pr = (i + 1) & 3;
        c.wait_w();
        if (i != 2) c.wait_a(pr);
        wg_fence();
        const uint32_t a = c.dA + pr * 1024, b = c.dW128 + c.ws * 1024;
        BODY4(wgmma_n64, 128, HI128, acc, a, b);
        BODY4(wgmma_n64, 128, HI128, acc, a + 512, b + 512);
        wg_commit();
        wg_wait<1>();
        if (i <= 10) c.rel_a(i & 3);
        c.rel_w(prev);
        prev = c.ws; c.adv_w();
      }
      wg_wait<0>();
      c.rel_w(prev);
      fence_regs(acc);
#pragma unroll
      for (int t = 0; t < 8; t++) {
        xres[2 * t] = badd2(xa[2 * t], badd2(yv[2 * t], pack2(acc[4 * t], acc[4 * t + 1])));
        xres[2 * t + 1] = badd2(xa[2 * t + 1], badd2(yv[2 * t + 1], pack2(acc[4 * t + 2], acc[4 * t + 3])));
      }
      c.put_tile(own, xres);
      if (l == 0) put_stats(c, xres);
      c.signal_stage();
    }
  }
}

__device__ __forceinline__ void producer_w(const KParams& p, uint32_t sb, int j, int cr) {
  const uint32_t bar = sb + SM_BAR;
  Spin sp{SPIN_BUDGET};
  uint32_t slot = 0, ph = 1;
  auto LD = [&](uint32_t dst, const CUtensorMap* m, int c0, int c1, uint32_t fb) {
    tma_load_2d_mc(dst, m, c0, c1, fb);
  };
  uint32_t lslot = NWS - WLIM, lph = 1;
#define W_BEGIN(BYTES)                                                              \
  {                                                                                 \
    if (WLIM < NWS) {                                                               \
      mbar_wait(sp, bar + B_FULLW + lslot * 8, lph);                                \
      if (++lslot == NWS) { lslot = 0; lph ^= 1; }                                  \
    }                                                                               \
    mbar_wait(sp, bar + B_EMPTYW + slot * 8, ph);                                   \
    const uint32_t d = sb + SM_W + slot * 16384, fb = bar + B_FULLW + slot * 8;     \
    if (elect_one()) {                                                              \
      mbar_expect_tx(fb, (BYTES));
#define W_END                                                                       \
    }                                                                               \
    if (++slot == NWS) { slot = 0; ph ^= 1; }                                       \
  }
#pragma unroll 1
  for (int l = 0; l < 2; l++) {
#pragma unroll 1
    for (int kb = 0; kb < 8; kb++) {
      W_BEGIN(16384)
        LD(d + cr * 8192, &p.mWqkv, 512 + 512 * cr + 64 * j, 64 * kb, fb);
      W_END
    }
#pragma unroll 1
    for (int i = 0; i < 4; i++) {
      W_BEGIN(16384)
        LD(d + cr * 8192, &p.mWqkv, 64 * j, 128 * i + 64 * cr, fb);
      W_END
    }
#pragma unroll 1
    for (int i = 0; i < 4; i++) {
      W_BEGIN(16384)
        LD(d + cr * 8192, &p.mWo, 64 * j, 128 * i + 64 * cr, fb);
      W_END
    }
#pragma unroll 1
    for (int i = 0; i < 4; i++) {
      W_BEGIN(16384)
        LD(d + cr * 8192, &p.mW1, 64 * j, 128 * i + 64 * cr, fb);
      W_END
    }
#pragma unroll 1
    for (int i = 0; i < 4; i++) {
      W_BEGIN(16384)
        LD(d + cr * 8192, &p.mW2, 64 * j, 128 * i + 64 * cr, fb);
      W_END
    }
#pragma unroll 1
    for (int kb = 0; kb < 8; kb++) {
      W_BEGIN(12288)
        LD(d + cr * 8192, &p.mW3, 224 * j + 64 * cr, 64 * kb, fb);
        if ((kb & 1) == cr) LD(d + 4096, &p.mW3, 224 * j + 32, 64 * kb, fb);
      W_END
    }
#pragma unroll 1
    for (int kb = 0; kb < 8; kb++) {
      W_BEGIN(16384)
        LD(d + cr * 8192, &p.mW3, 224 * j + 96 + 64 * cr, 64 * kb, fb);
        LD(d + cr * 8192 + 4096, &p.mW3, 224 * j + 128 + 64 * cr, 64 * kb, fb);
      W_END
    }
#pragma unroll 1
    for (int i = 0; i < 14; i++) {
      W_BEGIN(16384)
        int r0, r1;
        if (i == 5 || i == 6) { r0 = 224 * (4 * (i - 5) + 2 * cr) + 64; r1 = r0 + 224; }
        else {
          const int rr = i - 7;
          r0 = i == 2 ? 224 * j + 96 + 64 * cr
                      : (i < 5 ? 224 * ((i < 2 ? 2 * i : 2 * i - 2) + cr) : 224 * (rr + (rr >= j ? 1 : 0)) + 96 + 64 * cr);
          r1 = r0 + 32;
        }
        LD(d + cr * 8192, &p.mW4, 64 * j, r0, fb);
        LD(d + cr * 8192 + 4096, &p.mW4, 64 * j, r1, fb);
      W_END
    }
  }
#undef W_BEGIN
#undef W_END
}

__device__ __forceinline__ void publisher(const KParams& p, uint32_t sb, int h, int g, int j) {
  const uint32_t bar = sb + SM_BAR, abase = sb + SM_A + h * 65536, own = abase + j * 8192;
  const int blk = 2 * g + h;
  Spin sp{SPIN_BUDGET};
  uint32_t sc = 0;
  const uint32_t epoch = ld_relaxed(g_epoch + blockIdx.x * 8) + 1;
  auto wait_stage = [&]() {
    mbar_wait(sp, bar + B_STG + h * 32 + (sc & 3) * 8, (sc >> 2) & 1);
    sc++;
  };
  auto finish = [&](uint32_t* flag) {
    bulk_commit();
    bulk_wait0();
    fence_release_gpu();
    st_relaxed(flag, epoch);
  };
  uint32_t pc = 0;
  auto announce = [&]() {
    if (elect_one()) mbar_arrive(bar + B_PUBD + h * 32 + (pc & 3) * 8);
    pc++;
  };
  auto store_stats = [&](int l, int type) {
    bulk_store(g_stats + (((l * 3 + type) * 32 + blk) * 8 + j) * 64, sb + SM_STATS + h * 512, 512);
  };
  wait_stage();
  announce();
  if (elect_one()) { store_stats(0, 0); finish(flag_ptr(0, T_Q, blk) + j); }
  __syncwarp();
#pragma unroll 1
  for (int l = 0; l < 2; l++) {
    if (h == 1) {
      mbar_wait(sp, bar + B_HALOOUT, l);
      if (g < 15 && elect_one()) {
        bulk_store(g_halo + (l * 128 + g * 8 + j) * 256, sb + SM_HALO_OUT, 4096);
        finish(g_hflag + (l * 128 + g * 8 + j) * 8);
      }
      __syncwarp();
    }
#pragma unroll 1
    for (int e = 0; e < 4; e++) {
      const int buf = e == 0 ? BUF_O : (e == 1 ? BUF_XA : (e == 2 ? BUF_H + l : BUF_Y));
      uint32_t* flag = flag_ptr(l, T_O + e, blk) + j;
      wait_stage();
      announce();
      if (elect_one()) {
        tma_store_4d(&p.mActS, 0, 64 * blk, j, buf, own);
        if (e & 1) store_stats(l, (e + 1) >> 1);
        bulk_commit();
        bulk_wait0();
        fence_release_gpu();
        st_relaxed(flag, epoch);
      }
      __syncwarp();
    }
#pragma unroll 1
    for (int e = 0; e < 4; e++) {
      wait_stage();
      announce();
      if (elect_one()) {
        if (e == 0) tma_store_3d(&p.mH2aS, 0, 64 * blk, j, abase);
        else if (e == 1) {
#pragma unroll
          for (int w = 0; w < 4; w++) tma_store_3d(&p.mH2a32, 32 * (j & 1), 64 * blk + 16 * w, 8 + (j >> 1), abase + 8192 + w * 2048);
        } else tma_store_3d(&p.mH2bS, 0, 64 * blk, 2 * j + (e - 2), abase + (4 + e) * 8192);
        bulk_commit();
        if (e != 2) {
          bulk_wait0();
          if (e & 1) mbar_arrive(bar + B_SFREE + h * 8);
          fence_release_gpu();
          st_relaxed(flag_ptr(l, T_H2A0 + e, blk) + j, epoch);
        }
      }
      __syncwarp();
    }
    wait_stage();
    if (l == 0) announce();
    if (elect_one()) {
      if (l == 0) {
        tma_store_4d(&p.mActS, 0, 64 * blk, j, BUF_XB, own);
        store_stats(1, 0);
        finish(flag_ptr(1, T_Q, blk) + j);
      } else {
        tma_store_2d(&p.mOut, 64 * j, 64 * blk, own);
        bulk_commit();
        if (h == 0) st_relaxed(g_epoch + blockIdx.x * 8, epoch);
        bulk_wait0();
      }
    }
    __syncwarp();
  }
}

struct Loader {
  Spin sp;
  uint32_t sb, bar, epoch, abase, fbase;
  int h, j, g, blk, lane;
  uint32_t aph, emask;
  __device__ __forceinline__ void wait_own() {
    mbar_wait(sp, bar + B_PUBD + h * 32 + (aph & 3) * 8, (aph >> 2) & 1);
    aph++;
  }
  __device__ __forceinline__ void gather(const KParams& p, int l, int buf, int ftype, bool shift, bool stats) {
    const int r = lane & 7;
    const uint32_t* f0 = flag_ptr(l, ftype, blk) + r;
    const uint32_t* f1 = f0;
    if (shift) {
      const int nb = blk + (((r >> 1) & 1) ? 1 : -1);
      if (nb >= 0 && nb < 32) f1 = flag_ptr(l, ftype, nb) + r;
    }
    const uint32_t* f = lane < 8 ? f0 : f1;
    uint32_t issued = 0;
    while (true) {
      const uint32_t mm = __ballot_sync(0xffffffffu, ld_relaxed(f) == epoch);
      const uint32_t m = mm & (mm >> 8);
      const uint32_t fresh = m & (m >> 1) & 0x55u & ~issued;
      if (fresh) {
        fence_acquire_for_tma();
        issued |= fresh;
        if (elect_one()) {
#pragma unroll
          for (int pr = 0; pr < 4; pr++) {
            if (fresh & (1u << (2 * pr))) {
              const int sh = shift ? ((pr & 1) ? (pr >> 1) + 1 : -((pr >> 1) + 1)) : 0;
              mbar_expect_tx(fbase + pr * 8, 16384);
              tma_load_4d(abase + pr * 16384, &p.mActL, 0, 64 * blk + sh, 2 * pr, buf, fbase + pr * 8);
            }
          }
        }
        __syncwarp();
        if (issued == 0x55u) break;
      } else {
        if (sp.fail(16)) break;
        if (POLL_NS) __nanosleep(POLL_NS);
      }
    }
    if (stats && elect_one()) mbar_arrive(bar + B_STAT + h * 8);
  }
  __device__ __forceinline__ void wait_flags8(int l, int type) {
    poll_all(flag_ptr(l, type, blk) + (lane & 7));
  }
  __device__ __forceinline__ void poll_all(const uint32_t* f) {
    while (!__all_sync(0xffffffffu, ld_relaxed(f) == epoch)) {
      if (sp.fail(16)) break;
      if (POLL_NS) __nanosleep(POLL_NS);
    }
    fence_acquire_for_tma();
  }
  __device__ __forceinline__ void load_h2_pair(const CUtensorMap* m, int kb, uint32_t pair, bool wait_empty) {
    if (wait_empty) {
      mbar_wait(sp, bar + B_EMPTYA + h * 32 + pair * 8, (emask >> pair) & 1);
      emask ^= 1u << pair;
    }
    if (elect_one()) {
      mbar_expect_tx(fbase + pair * 8, 16384);
      tma_load_3d(abase + pair * 16384, m, 0, 64 * blk, kb, fbase + pair * 8);
    }
  }
};

__device__ __forceinline__ void loader(const KParams& p, uint32_t sb, int h, int g, int j) {
  Loader L;
  L.sb = sb; L.bar = sb + SM_BAR; L.h = h; L.j = j; L.g = g; L.blk = 2 * g + h;
  L.abase = sb + SM_A + h * 65536; L.fbase = sb + SM_BAR + B_FULLA + h * 32;
  L.sp.left = SPIN_BUDGET;
  L.lane = threadIdx.x & 31; L.aph = 0; L.emask = 0;
  const int blk = L.blk;
  if (elect_one()) {
#pragma unroll
    for (int i = 0; i < 4; i++) {
      const int pr = ((j >> 1) + i) & 3;
      mbar_expect_tx(L.fbase + pr * 8, 16384);
      tma_load_2d(L.abase + pr * 16384, &p.mXin, 128 * pr, 64 * blk, L.fbase + pr * 8);
      tma_load_2d(L.abase + pr * 16384 + 8192, &p.mXin, 128 * pr + 64, 64 * blk, L.fbase + pr * 8);
    }
  }
  __syncwarp();
  const uint32_t epoch = ld_relaxed(g_epoch + blockIdx.x * 8) + 1;
  L.epoch = epoch;
  L.wait_own();
  L.wait_flags8(0, T_Q);
  if (elect_one()) mbar_arrive(L.bar + B_STAT + h * 8);
#pragma unroll 1
  for (int l = 0; l < 2; l++) {
    if (h == 0 && g > 0) {
      mbar_wait(L.sp, L.bar + B_HALOOUT, l);
      if (HALO_NS) __nanosleep(HALO_NS);
      L.poll_all(g_hflag + (l * 128 + (g - 1) * 8 + j) * 8);
      if (elect_one()) {
        mbar_expect_tx(L.bar + B_HALOIN, 4096);
        bulk_load(sb + SM_HALO_IN, g_halo + (l * 128 + (g - 1) * 8 + j) * 256, 4096, L.bar + B_HALOIN);
      }
      __syncwarp();
    }
#pragma unroll 1
    for (int e = 0; e < 4; e++) {
      const int buf = e == 0 ? BUF_O : (e == 1 ? BUF_XA : (e == 2 ? BUF_H + l : BUF_Y));
      L.wait_own();
      L.gather(p, l, buf, T_O + e, e == 2, (e & 1) != 0);
    }
#pragma unroll 1
    for (int i = 0; i < 14; i++) {
      if (i == 2) continue;
      if (i == 0 || i == 5 || i == 7) {
        L.wait_own();
        if (i == 7) L.wait_own();
        L.wait_flags8(l, i == 0 ? T_H2A0 : (i == 5 ? T_H2A1 : T_H2B));
      }
      const uint32_t pr = (i + 1) & 3;
      if (i == 3 || i == 6) mbar_wait(L.sp, L.bar + B_SFREE + h * 8, i == 6);
      const int rr = i - 7, rk = rr + (rr >= j ? 1 : 0);
      const int slab = i < 2 ? 2 * i : (i < 7 ? 2 * i - 2 : 2 * rk);
      L.load_h2_pair(i < 7 ? &p.mH2aL : &p.mH2bL, slab, pr, i != 3);
    }
    if (l == 0) {
      L.wait_own();
      L.gather(p, 1, BUF_XB, T_Q, false, true);
    }
  }
}

__device__ __forceinline__ const char* colsum_src(const KParams& p, int j, int task, int lane, int& ld) {
  const int u = task >> 2, qd = task & 3;
  const __nv_bfloat16* W;
  if (u < 6) { W = p.wqkv + ((u >> 1) == 0 ? 512 : ((u >> 1) == 1 ? 1024 : 0)) + 64 * j + 32 * (u & 1); ld = 1536; }
  else if (u < 8) { W = p.w1 + 64 * j + 32 * (u - 6); ld = 512; }
  else { W = p.w3 + 224 * j + 32 * (u - 8); ld = 1792; }
  return (const char*)(W + (size_t)(qd * 128 + (lane >> 2)) * ld + (lane & 3) * 8);
}
__device__ __forceinline__ void colsum_acc(float (&s)[8], const uint4& v) {
  s[0] += bf_lo(v.x); s[1] += bf_hi(v.x); s[2] += bf_lo(v.y); s[3] += bf_hi(v.y);
  s[4] += bf_lo(v.z); s[5] += bf_hi(v.z); s[6] += bf_lo(v.w); s[7] += bf_hi(v.w);
}
__device__ __forceinline__ void colsum_worker(const KParams& p, uint32_t sb, int g, int j, int cw, float (&s)[8]) {
  const int lane = threadIdx.x & 31;
  const uint32_t epoch = ld_relaxed(g_epoch + blockIdx.x * 8) + 1;
  const int wi = 2 * g + cw;
#pragma unroll 1
  for (int round = 0; round < 2; round++) {
    const int task = round == 0 ? wi : 32 + wi;
    if (task >= 60) break;
    const int u = task >> 2, qd = task & 3;
    if (round == 1) {
      int ld;
      const char* src = colsum_src(p, j, task, lane, ld);
      zero_regs(s);
#pragma unroll 1
      for (int b = 0; b < 2; b++) {
        uint4 v[8];
#pragma unroll
        for (int r = 0; r < 8; r++) v[r] = __ldg((const uint4*)(src + (size_t)(b * 8 + r) * 8 * ld * 2));
#pragma unroll
        for (int r = 0; r < 8; r++) colsum_acc(s, v[r]);
      }
    }
#pragma unroll
    for (int i = 0; i < 8; i++) {
      s[i] += __shfl_xor_sync(0xffffffffu, s[i], 4);
      s[i] += __shfl_xor_sync(0xffffffffu, s[i], 8);
      s[i] += __shfl_xor_sync(0xffffffffu, s[i], 16);
    }
    const uint32_t stg = sb + SM_CSTG + cw * 128;
    if (lane < 4) {
      sts128(stg + lane * 32, __float_as_uint(s[0]), __float_as_uint(s[1]), __float_as_uint(s[2]), __float_as_uint(s[3]));
      sts128(stg + lane * 32 + 16, __float_as_uint(s[4]), __float_as_uint(s[5]), __float_as_uint(s[6]), __float_as_uint(s[7]));
    }
    fence_async_smem();
    __syncwarp();
    if (elect_one()) {
      bulk_store(g_csum + (j * 4 + qd) * 480 + 32 * u, stg, 128);
      bulk_commit();
      bulk_wait0();
      fence_release_gpu();
      st_relaxed(g_cflag + j * 64 + task, epoch);
    }
    __syncwarp();
  }
}

template <int U0, int NU>
__device__ __forceinline__ void csum_fetch(Spin& sp, uint32_t sb, int j, uint32_t epoch, int part) {
  const int lane = threadIdx.x & 31;
  const uint32_t* f = g_cflag + j * 64 + 4 * U0 + (lane < 4 * NU ? lane : 0);
  while (!__all_sync(0xffffffffu, ld_relaxed(f) == epoch))
    if (sp.fail(8)) break;
  asm volatile("fence.acquire.gpu;" ::: "memory");
  const uint32_t* src = (const uint32_t*)g_csum + j * 4 * 480 + 32 * U0 + lane;
  uint32_t v[NU][4];
#pragma unroll
  for (int u = 0; u < NU; u++)
#pragma unroll
    for (int k = 0; k < 4; k++) v[u][k] = ld_relaxed(src + 32 * u + 480 * k);
#pragma unroll
  for (int u = 0; u < NU; u++) {
    const float t = (__uint_as_float(v[u][0]) + __uint_as_float(v[u][1])) + (__uint_as_float(v[u][2]) + __uint_as_float(v[u][3]));
    asm volatile("st.shared.f32 [%0], %1;" ::"r"(sb + SM_CSUM + (32 * (U0 + u) + lane) * 4), "f"(t) : "memory");
  }
  __syncwarp();
  if (elect_one()) mbar_arrive(sb + SM_BAR + B_CRDY + part * 8);
  __syncwarp();
}
__device__ __forceinline__ void helper(const KParams& p, uint32_t sb, int g, int j) {
  Spin sp{SPIN_BUDGET};
  const uint32_t epoch = ld_relaxed(g_epoch + blockIdx.x * 8) + 1;
  csum_fetch<0, 6>(sp, sb, j, epoch, 0);
  if (elect_one()) {
    const int b = g * 8 + j;
    l2_prefetch((const char*)p.wo + b * 4096, 4096);
    l2_prefetch((const char*)p.w2 + b * 4096, 4096);
    l2_prefetch((const char*)p.w4 + b * 14336, 14336);
  }
  __syncwarp();
  csum_fetch<6, 2>(sp, sb, j, epoch, 1);
  csum_fetch<8, 7>(sp, sb, j, epoch, 2);
}

__global__ void
__cluster_dims__(2, 1, 1)
__launch_bounds__(NTHREADS, 1) fused_kernel(const __grid_constant__ KParams p) {
  extern __shared__ __align__(1024) uint8_t smem[];
  const uint32_t sb = smem_u32(smem);
  const int cl = blockIdx.x >> 1, cr = blockIdx.x & 1;
  int set, j;
  if (cl < 4) { set = 3; j = 4 + cl; }
  else if (cl < 36) { set = (cl - 4) & 7; j = (cl - 4) >> 3; }
  else { const int a = (cl - 36) % 7; set = a < 3 ? a : a + 1; j = 4 + (cl - 36) / 7; }
  const int g = 2 * set + cr;
  const uint32_t bar = sb + SM_BAR;
  uint4 cv[16];
  {
    int ld;
    const char* src = colsum_src(p, j, 2 * g + ((threadIdx.x >> 5) & 1), threadIdx.x & 31, ld);
    const uint32_t on = threadIdx.x >= 448;
#pragma unroll
    for (int r = 0; r < 16; r++)
      asm volatile("{\n.reg .pred p;\nsetp.ne.u32 p, %5, 0;\nmov.b32 %0, 0;\nmov.b32 %1, 0;\nmov.b32 %2, 0;\nmov.b32 %3, 0;\n"
                   "@p ld.global.nc.v4.u32 {%0, %1, %2, %3}, [%4];\n}"
                   : "=r"(cv[r].x), "=r"(cv[r].y), "=r"(cv[r].z), "=r"(cv[r].w) : "l"(src + (size_t)r * 8 * ld * 2), "r"(on));
  }
  if (threadIdx.x == 0) {
    for (int i = 0; i < NWS; i++) { mbar_init(bar + B_FULLW + i * 8, 1); mbar_init(bar + B_EMPTYW + i * 8, 16); }
    for (int i = 0; i < 8; i++) { mbar_init(bar + B_FULLA + i * 8, 1); mbar_init(bar + B_EMPTYA + i * 8, 4); }
    for (int i = 0; i < 8; i++) mbar_init(bar + B_STG + i * 8, 4);
    for (int i = 0; i < 2; i++) mbar_init(bar + B_STAT + i * 8, 1);
    mbar_init(bar + B_HALOIN, 1); mbar_init(bar + B_HALOOUT, 1); mbar_init(bar + B_XWG, 1);
    for (int i = 0; i < 3; i++) mbar_init(bar + B_CRDY + i * 8, 1);
    for (int i = 0; i < 8; i++) mbar_init(bar + B_PUBD + i * 8, 1);
    mbar_init(bar + B_SFREE, 1); mbar_init(bar + B_SFREE + 8, 1);
    asm volatile("fence.mbarrier_init.release.cluster;" ::: "memory");
  }
  __syncthreads();
  cluster_sync_relaxed();
  const int wg = __shfl_sync(0xffffffffu, threadIdx.x >> 7, 0);
  if (wg == 3) {
    float cs[8];
    zero_regs(cs);
#pragma unroll
    for (int r = 0; r < 16; r++) colsum_acc(cs, cv[r]);
    asm volatile("setmaxnreg.dec.sync.aligned.u32 56;");
    const int w = __shfl_sync(0xffffffffu, (threadIdx.x >> 5) & 3, 0);
    if (w < 2) publisher(p, sb, w, g, j);
    else colsum_worker(p, sb, g, j, w - 2, cs);
    __syncwarp();
    cluster_sync_relaxed();
  } else if (wg == 2) {
    asm volatile("setmaxnreg.dec.sync.aligned.u32 56;");
    const int w = __shfl_sync(0xffffffffu, (threadIdx.x >> 5) & 3, 0);
    if (w == 0) {
      producer_w(p, sb, j, cr);
    } else if (w == 3) {
      helper(p, sb, g, j);
    } else {
      loader(p, sb, w - 1, g, j);
    }
    __syncwarp();
    cluster_sync_relaxed();
  } else {
    asm volatile("setmaxnreg.inc.sync.aligned.u32 200;");
    consumer(p, sb, wg, g, j);
    cluster_sync_relaxed();
  }
}

typedef CUresult (*EncodeFn)(CUtensorMap*, CUtensorMapDataType, cuuint32_t, void*, const cuuint64_t*, const cuuint64_t*,
                             const cuuint32_t*, const cuuint32_t*, CUtensorMapInterleave, CUtensorMapSwizzle,
                             CUtensorMapL2promotion, CUtensorMapFloatOOBfill);

static void make_map(EncodeFn enc, CUtensorMap* m, const void* base, uint64_t d0, uint64_t d1, uint32_t b0, uint32_t b1,
                     CUtensorMapSwizzle sw) {
  cuuint64_t dims[2] = {d0, d1};
  cuuint64_t strides[1] = {d0 * 2};
  cuuint32_t box[2] = {b0, b1};
  cuuint32_t es[2] = {1, 1};
  enc(m, CU_TENSOR_MAP_DATA_TYPE_BFLOAT16, 2, const_cast<void*>(base), dims, strides, box, es,
      CU_TENSOR_MAP_INTERLEAVE_NONE, sw, CU_TENSOR_MAP_L2_PROMOTION_L2_128B, CU_TENSOR_MAP_FLOAT_OOB_FILL_NONE);
}
static void make_slab_map(EncodeFn enc, CUtensorMap* m, const void* base, int rank, uint64_t nslab, uint64_t nbuf,
                          uint32_t b0, uint32_t b1, uint32_t b2, CUtensorMapSwizzle sw) {
  cuuint64_t dims[4] = {64, (cuuint64_t)S_, nslab, nbuf};
  cuuint64_t strides[3] = {128, (cuuint64_t)S_ * 128, (cuuint64_t)S_ * 128 * nslab};
  cuuint32_t box[4] = {b0, b1, b2, 1};
  cuuint32_t es[4] = {1, 1, 1, 1};
  enc(m, CU_TENSOR_MAP_DATA_TYPE_BFLOAT16, (cuuint32_t)rank, const_cast<void*>(base), dims, strides, box, es,
      CU_TENSOR_MAP_INTERLEAVE_NONE, sw, CU_TENSOR_MAP_L2_PROMOTION_L2_128B, CU_TENSOR_MAP_FLOAT_OOB_FILL_NONE);
}

}

extern "C" void kernel_launch(void* const* d_in, const int* in_sizes, int n_in, void* d_out, int out_size) {
  using namespace fk;
  (void)in_sizes; (void)n_in; (void)out_size;
  static EncodeFn enc = nullptr;
  static void *act = nullptr, *h2a = nullptr, *h2b = nullptr;
  if (!enc) {
    void* fn = nullptr;
    cudaDriverEntryPointQueryResult st;
    cudaGetDriverEntryPoint("cuTensorMapEncodeTiled", &fn, cudaEnableDefault, &st);
    enc = (EncodeFn)fn;
    cudaGetSymbolAddress(&act, g_act);
    cudaGetSymbolAddress(&h2a, g_h2a);
    cudaGetSymbolAddress(&h2b, g_h2b);
    cudaFuncSetAttribute(fused_kernel, cudaFuncAttributeMaxDynamicSharedMemorySize, SM_TOTAL);
  }
  KParams p;
  p.x = (const __nv_bfloat16*)d_in[0];
  p.wqkv = (const __nv_bfloat16*)d_in[1];
  p.wo = (const __nv_bfloat16*)d_in[2];
  p.w1 = (const __nv_bfloat16*)d_in[4];
  p.w2 = (const __nv_bfloat16*)d_in[5];
  p.w3 = (const __nv_bfloat16*)d_in[6];
  p.w4 = (const __nv_bfloat16*)d_in[7];
  const CUtensorMapSwizzle S128 = CU_TENSOR_MAP_SWIZZLE_128B, S64 = CU_TENSOR_MAP_SWIZZLE_64B;
  make_map(enc, &p.mXin, p.x, D_, S_, 64, 64, S128);
  make_map(enc, &p.mOut, d_out, D_, S_, 64, 64, S128);
  make_slab_map(enc, &p.mActL, act, 4, 8, NBUF, 64, 64, 2, S128);
  make_slab_map(enc, &p.mActS, act, 4, 8, NBUF, 64, 64, 1, S128);
  make_slab_map(enc, &p.mH2aL, h2a, 3, 12, 1, 64, 64, 2, S128);
  make_slab_map(enc, &p.mH2aS, h2a, 3, 12, 1, 64, 64, 1, S128);
  make_slab_map(enc, &p.mH2a32, h2a, 3, 12, 1, 32, 16, 1, S64);
  make_slab_map(enc, &p.mH2bL, h2b, 3, 16, 1, 64, 64, 2, S128);
  make_slab_map(enc, &p.mH2bS, h2b, 3, 16, 1, 64, 64, 1, S128);
  make_map(enc, &p.mWqkv, p.wqkv, 1536, 512, 64, 64, S128);
  make_map(enc, &p.mWo, p.wo, 512, 512, 64, 64, S128);
  make_map(enc, &p.mW1, p.w1, 512, 512, 64, 64, S128);
  make_map(enc, &p.mW2, p.w2, 512, 512, 64, 64, S128);
  make_map(enc, &p.mW3, p.w3, 1792, 512, 32, 64, S64);
  make_map(enc, &p.mW4, p.w4, 512, 1792, 64, 32, S128);
  fused_kernel<<<NCTA, NTHREADS, SM_TOTAL, cudaStreamPerThread>>>(p);
}
```
